```python
import torch

def _softmax(x, axis=-1):
    return torch.softmax(x, dim=axis)
def _gelu(x):
    return torch.nn.functional.gelu(x, approximate="tanh")
def _silu(x):
    return torch.nn.functional.silu(x)
def _sigmoid(x):
    return torch.sigmoid(x)
def _layernorm(x, axis=-1, eps=1e-5):
    m = x.mean(dim=axis, keepdim=True)
    v = x.var(dim=axis, keepdim=True, unbiased=False)
    return (x - m) / torch.sqrt(v + eps)
def _scatter_add(tgt, idx, src, axis=0):
    return tgt.clone().index_add_(axis, idx, src)
def _segment_sum(src, seg, n):
    out = torch.zeros((n,) + src.shape[1:], dtype=src.dtype)
    return out.index_add_(0, seg, src)
def _pad(x, pw):
    flat = tuple(v for pair in reversed(pw) for v in pair)
    return torch.nn.functional.pad(x, flat)

kernel_name = 'parallel_sum__sliding_block__mixer_channel_mlp__prompt'

def setup_inputs():

    _w = (lambda a: (lambda t: t.to(torch.bfloat16) if t.is_floating_point() else t)(torch.as_tensor(a)))
    def _A_setup():
        B, S, D = 1, 2048, 512
        return {
            "x": _w((lambda *s: torch.randn(*s, dtype=torch.bfloat16) * 0.05)(B, S, D)),
            "wqkv": _w((lambda *s: torch.randn(*s, dtype=torch.bfloat16) * 0.05)(D, 3 * D)),
            "wo": _w((lambda *s: torch.randn(*s, dtype=torch.bfloat16) * 0.05)(D, D)),
        }
    _A_in = _A_setup()

    def _B_setup():
        B, S, D, F = 1, 2048, 512, 1376
        return {
            "x": _w((lambda *s: torch.randn(*s, dtype=torch.bfloat16) * 0.05)(B, S, D)),
            "w1": _w((lambda *s: torch.randn(*s, dtype=torch.bfloat16) * 3.2)(D, F) * (D ** -0.5)),
            "b1": _w((lambda *s: torch.randn(*s, dtype=torch.bfloat16) * 1.6)(F)),
            "w2": _w((lambda *s: torch.randn(*s, dtype=torch.bfloat16) * 0.2)(F, D) * (F ** -0.5)),
            "b2": _w((lambda *s: torch.randn(*s, dtype=torch.bfloat16) * 0.2)(D)),
        }
    _B_in = _B_setup()

    return {
        "A_x": _A_in["x"],
        "A_wqkv": _A_in["wqkv"],
        "A_wo": _A_in["wo"],
        "B_x": _B_in["x"],
        "B_w1": _B_in["w1"],
        "B_b1": _B_in["b1"],
        "B_w2": _B_in["w2"],
        "B_b2": _B_in["b2"],
    }

def reference(A_x, A_wqkv, A_wo, B_x, B_w1, B_b1, B_w2, B_b2):
    def _A_ref(x, wqkv, wo):
        B, S, D = x.shape
        H = 32; Dh = D // H; W = 256
        qkv = (lambda x, *d: x.permute(*d))((x @ wqkv).reshape(B, S, 3, H, Dh), 2, 0, 3, 1, 4)
        q, k, v = qkv[0], qkv[1], qkv[2]
        scores = torch.einsum("bhqd,bhkd->bhqk", q, k) * (Dh ** -0.5)
        idx = torch.arange(S)
        mask = (idx[:, None] - idx[None, :] >= 0) & (idx[:, None] - idx[None, :] < W)
        scores = torch.where(mask[None, None], scores, -1e9)
        p = _softmax(scores, axis=-1)
        o = torch.einsum("bhqk,bhkd->bhqd", p, v)
        return (lambda x, *d: x.permute(*d))(o, 0, 2, 1, 3).reshape(B, S, D) @ wo

    def _B_ref(x, w1, b1, w2, b2):
        y = _layernorm(x, axis=-1)
        h = _gelu(torch.einsum("bsd,df->bsf", y, w1) + b1)
        return torch.einsum("bsf,fd->bsd", h, w2) + b2

    x = A_x
    xn = _layernorm(x, axis=-1)
    return x + _A_ref(xn, A_wqkv, A_wo) + _B_ref(xn, B_w1, B_b1, B_w2, B_b2)
```

```cpp
#include <cuda_runtime.h>
#include <cuda_bf16.h>
#include <cuda.h>
#include <stdint.h>

namespace {

constexpr int NTHREADS = 640;
constexpr uint32_t SB0 = 1024;
constexpr uint32_t XP = 17408;
constexpr uint32_t OFF_X = 0;
constexpr uint32_t OFF_BIAS = 16384 + 128;
constexpr uint32_t OFF_ST = 16384 + 256;
constexpr uint32_t OFF_Q0 = 16384 + 512;
constexpr uint32_t OFF_W = 8 * XP;
constexpr uint32_t OFF_KV = OFF_W + 65536;
constexpr uint32_t KV_V2 = 0, KV_K1 = 2048, KV_V1 = 4096, KV_V0 = 12288, KV_ONES = 16384, KV_K0 = 18432, KV_K2 = 22528;
constexpr uint32_t OFF_BAR = OFF_KV + 26624;
constexpr int B_AF = 0  , B_WF = 8  , B_WE = 16  , B_ATT = 24  , B_PUB = 32  , B_XINIT = 41, B_GRP = 42  , B_STAT = 48, B_SLOT = 49  , B_KV0 = 53  , B_HT = 59  , B_O3 = 83  , B_COUNT = 87;
constexpr int NB_OUT = 1, NB_Q = 2, NB_ORD = 5  ;
constexpr uint32_t SMEM_BYTES = OFF_BAR + B_COUNT * 8;
constexpr int SPIN_LIMIT = 1 << 17;

constexpr int SLEEP_SHORT = 20;
constexpr int SLEEP_LONG = 64;
constexpr int ODELAY = 150;
constexpr int TAIL = 6;
constexpr int TAILE = 4;
constexpr int KDELAY = 150;
constexpr int SPF = 1;
constexpr int MID = 12;
constexpr int LAG = 2;
constexpr int PFAT = 0;
constexpr int ORDER = 0x541320;
constexpr int PUBORD = 0x653120;
constexpr int NPUB = 6;
constexpr int PF = 2;
constexpr int DEPTH = 5;

__device__ uint32_t g_epoch[128 * 32];
__device__ uint32_t g_flags[128 * 32];
__device__ __align__(128) unsigned char g_kv[32 * 6 * 32768];
__device__ __align__(128) unsigned char g_h[128 * 3 * 16384];
__device__ __align__(128) unsigned char g_o[16 * 8 * 16384];

__device__ __forceinline__ uint32_t smem_u32(const void* p) { return (uint32_t)__cvta_generic_to_shared(p); }
__device__ __forceinline__ void mbar_init(uint32_t bar, uint32_t cnt) { asm volatile("mbarrier.init.shared::cta.b64 [%0], %1;" ::"r"(bar), "r"(cnt) : "memory"); }
__device__ __forceinline__ void mbar_expect_tx(uint32_t bar, uint32_t bytes) { asm volatile("mbarrier.arrive.expect_tx.shared::cta.b64 _, [%0], %1;" ::"r"(bar), "r"(bytes) : "memory"); }
__device__ __forceinline__ void mbar_expect_only(uint32_t bar, uint32_t bytes) { asm volatile("mbarrier.expect_tx.relaxed.cta.shared::cta.b64 [%0], %1;" ::"r"(bar), "r"(bytes) : "memory"); }
__device__ __forceinline__ void mbar_arrive(uint32_t bar) { asm volatile("mbarrier.arrive.shared::cta.b64 _, [%0];" ::"r"(bar) : "memory"); }
__device__ __forceinline__ void st_relaxed_if(uint32_t* p, uint32_t v, bool c) {
  asm volatile("{ .reg .pred p; setp.ne.u32 p, %2, 0; @p st.relaxed.gpu.global.u32 [%0], %1; }" ::"l"(p), "r"(v), "r"((uint32_t)c) : "memory");
}
__device__ __forceinline__ uint32_t nonzero(uint32_t w) { return max(w, 1u); }
__device__ __forceinline__ bool mbar_test(uint32_t bar, uint32_t parity) {
  uint32_t ok;
  asm volatile("{ .reg .pred p; mbarrier.test_wait.parity.shared::cta.b64 p, [%1], %2; selp.u32 %0, 1, 0, p; }" : "=r"(ok) : "r"(bar), "r"(parity) : "memory");
  return ok != 0;
}
__device__ __forceinline__ void mbar_wait(uint32_t bar, uint32_t parity) {
  asm volatile(
      "{ .reg .pred p; .reg .u32 n;\n"
      "mbarrier.try_wait.parity.shared::cta.b64 p, [%0], %1;\n"
      "@p bra.uni DONE_%=;\n"
      "mov.u32 n, 0;\n"
      "WAIT_%=: nanosleep.u32 %3;\n"
      "mbarrier.try_wait.parity.shared::cta.b64 p, [%0], %1;\n"
      "@p bra.uni DONE_%=;\n"
      "add.u32 n, n, 1; setp.lt.u32 p, n, %2;\n"
      "@p bra.uni WAIT_%=;\n"
      "DONE_%=: }" ::"r"(bar), "r"(parity), "n"(SPIN_LIMIT * 8), "n"(SLEEP_SHORT) : "memory");
}
__device__ __forceinline__ void mbar_wait_sleep(uint32_t bar, uint32_t parity) {
  asm volatile(
      "{ .reg .pred p; .reg .u32 n; mov.u32 n, 0;\n"
      "WAIT_%=: mbarrier.try_wait.parity.shared::cta.b64 p, [%0], %1;\n"
      "@p bra.uni DONE_%=;\n"
      "nanosleep.u32 %3;\n"
      "add.u32 n, n, 1; setp.lt.u32 p, n, %2;\n"
      "@p bra.uni WAIT_%=;\n"
      "DONE_%=: }" ::"r"(bar), "r"(parity), "n"(SPIN_LIMIT), "n"(SLEEP_LONG) : "memory");
}
__device__ __forceinline__ void mbar_arrive_warp(uint32_t bar) {
  asm volatile("{ .reg .pred p; elect.sync _|p, 0xffffffff; @p mbarrier.arrive.shared::cta.b64 _, [%0]; }" ::"r"(bar) : "memory");
}
__device__ __forceinline__ void mbar_arrive_warp_if(uint32_t bar, bool c) {
  asm volatile("{ .reg .pred p, q; elect.sync _|p, 0xffffffff; setp.ne.and.u32 q, %1, 0, p; @q mbarrier.arrive.shared::cta.b64 _, [%0]; }" ::"r"(bar), "r"((uint32_t)c) : "memory");
}
__device__ __forceinline__ void nb_sync(int id, int n) { asm volatile("bar.sync %0, %1;" ::"r"(id), "r"(n) : "memory"); }
__device__ __forceinline__ void nb_arrive(int id, int n) { asm volatile("bar.arrive %0, %1;" ::"r"(id), "r"(n) : "memory"); }
__device__ __forceinline__ bool elect_one() {
  uint32_t p;
  asm volatile("{ .reg .pred p; elect.sync _|p, 0xffffffff; selp.u32 %0, 1, 0, p; }" : "=r"(p));
  return p != 0;
}
__device__ __forceinline__ void tma2d(uint32_t dst, const CUtensorMap* m, int c0, int c1, uint32_t bar) {
  asm volatile("cp.async.bulk.tensor.2d.shared::cluster.global.mbarrier::complete_tx::bytes [%0], [%1, {%3, %4}], [%2];" ::"r"(dst), "l"(m), "r"(bar), "r"(c0), "r"(c1) : "memory");
}
__device__ __forceinline__ void tma3d(uint32_t dst, const CUtensorMap* m, int c0, int c1, int c2, uint32_t bar) {
  asm volatile("cp.async.bulk.tensor.3d.shared::cluster.global.mbarrier::complete_tx::bytes [%0], [%1, {%3, %4, %5}], [%2];" ::"r"(dst), "l"(m), "r"(bar), "r"(c0), "r"(c1), "r"(c2) : "memory");
}
__device__ __forceinline__ void bulk_ld(uint32_t dst, const void* src, uint32_t bytes, uint32_t bar) {
  asm volatile("cp.async.bulk.shared::cluster.global.mbarrier::complete_tx::bytes [%0], [%1], %2, [%3];" ::"r"(dst), "l"(src), "r"(bytes), "r"(bar) : "memory");
}
__device__ __forceinline__ void tma2d_store(const CUtensorMap* m, int c0, int c1, uint32_t src) {
  asm volatile("cp.async.bulk.tensor.2d.global.shared::cta.bulk_group [%0, {%2, %3}], [%1];" ::"l"(m), "r"(src), "r"(c0), "r"(c1) : "memory");
}
__device__ __forceinline__ void prefetch_map(const CUtensorMap* m) { asm volatile("prefetch.tensormap [%0];" ::"l"(m) : "memory"); }
__device__ __forceinline__ void l2_prefetch(const void* src, uint32_t bytes) { asm volatile("cp.async.bulk.prefetch.L2.global [%0], %1;" ::"l"(src), "r"(bytes) : "memory"); }
__device__ __forceinline__ uint32_t ld_acquire(const uint32_t* p) { uint32_t v; asm volatile("ld.acquire.gpu.global.u32 %0, [%1];" : "=r"(v) : "l"(p) : "memory"); return v; }
__device__ __forceinline__ uint32_t ld_relaxed(const uint32_t* p) { uint32_t v; asm volatile("ld.relaxed.gpu.global.u32 %0, [%1];" : "=r"(v) : "l"(p) : "memory"); return v; }
__device__ __forceinline__ void st_relaxed(uint32_t* p, uint32_t v) { asm volatile("st.relaxed.gpu.global.u32 [%0], %1;" ::"l"(p), "r"(v) : "memory"); }
__device__ __forceinline__ float lds_bf16(uint32_t a) { uint32_t v; asm volatile("ld.shared.u16 %0, [%1];" : "=r"(v) : "r"(a)); return __uint_as_float(v << 16); }
__device__ __forceinline__ uint32_t lds32u(uint32_t a) { uint32_t v; asm volatile("ld.shared.u32 %0, [%1];" : "=r"(v) : "r"(a) : "memory"); return v; }
__device__ __forceinline__ void sts32u(uint32_t a, uint32_t v) { asm volatile("st.shared.u32 [%0], %1;" ::"r"(a), "r"(v) : "memory"); }
__device__ __forceinline__ uint32_t mapa(uint32_t a, uint32_t rank) { uint32_t r; asm("mapa.shared::cluster.u32 %0, %1, %2;" : "=r"(r) : "r"(a), "r"(rank)); return r; }
__device__ __forceinline__ void st_async4(uint32_t a, float4 v, uint32_t bar) {
  asm volatile("st.async.shared::cluster.mbarrier::complete_tx::bytes.v4.f32 [%0], {%1,%2,%3,%4}, [%5];" ::"r"(a), "f"(v.x), "f"(v.y), "f"(v.z), "f"(v.w), "r"(bar) : "memory");
}
__device__ __forceinline__ void cluster_arrive() { asm volatile("barrier.cluster.arrive.relaxed.aligned;" ::: "memory"); }
__device__ __forceinline__ void cluster_wait() { asm volatile("barrier.cluster.wait.aligned;" ::: "memory"); }
__device__ __forceinline__ float rsqrt_fast(float x) { float y; asm("rsqrt.approx.ftz.f32 %0, %1;" : "=f"(y) : "f"(x)); return y; }
__device__ __forceinline__ float rcp_fast(float x) { float y; asm("rcp.approx.ftz.f32 %0, %1;" : "=f"(y) : "f"(x)); return y; }
__device__ __forceinline__ void sts128u(uint32_t a, uint32_t x, uint32_t y, uint32_t z, uint32_t w) { asm volatile("st.shared.v4.u32 [%0], {%1,%2,%3,%4};" ::"r"(a), "r"(x), "r"(y), "r"(z), "r"(w) : "memory"); }
__device__ __forceinline__ void fence_gpu() { asm volatile("fence.release.gpu;" ::: "memory"); }
__device__ __forceinline__ void fence_proxy_global() { asm volatile("fence.proxy.async.global;" ::: "memory"); }
__device__ __forceinline__ void fence_proxy_smem() { asm volatile("fence.proxy.async.shared::cta;" ::: "memory"); }
__device__ __forceinline__ void wg_fence() { asm volatile("wgmma.fence.sync.aligned;" ::: "memory"); }
__device__ __forceinline__ void wg_commit() { asm volatile("wgmma.commit_group.sync.aligned;" ::: "memory"); }
template <int N> __device__ __forceinline__ void wg_wait() { asm volatile("wgmma.wait_group.sync.aligned %0;" ::"n"(N) : "memory"); }
template <int N> __device__ __forceinline__ void pin(float (&d)[N]) {
#pragma unroll
  for (int i = 0; i < N; i++) asm volatile("" : "+f"(d[i])::"memory");
}
template <int N> __device__ __forceinline__ void pin(uint32_t (&d)[N]) {
#pragma unroll
  for (int i = 0; i < N; i++) asm volatile("" : "+r"(d[i])::"memory");
}
__host__ __device__ constexpr uint32_t desc_lo(uint32_t off, uint32_t lbo) { return ((SB0 + off) >> 4) | ((lbo >> 4) << 16); }
constexpr uint32_t HI_SW128 = (1024 >> 4) | (1u << 30), HI_SW64 = (512 >> 4) | (2u << 30);
__device__ __forceinline__ uint32_t pack_bf16(float lo, float hi) { uint32_t r; asm("cvt.rn.bf16x2.f32 %0, %1, %2;" : "=r"(r) : "f"(hi), "f"(lo)); return r; }
__device__ __forceinline__ float bf_lo(uint32_t v) { return __uint_as_float(v << 16); }
__device__ __forceinline__ float bf_hi(uint32_t v) { return __uint_as_float(v & 0xffff0000u); }
__device__ __forceinline__ float ex2(float x) { float y; asm("ex2.approx.ftz.f32 %0, %1;" : "=f"(y) : "f"(x)); return y; }
__device__ __forceinline__ void ex2_ip(float& x, int one) { asm("{ .reg .pred p; setp.ne.s32 p, %1, 0; @p ex2.approx.ftz.f32 %0, %0; }" : "+f"(x) : "r"(one)); }
__device__ __forceinline__ void mov_if(float& d, float s, bool c) { asm("{ .reg .pred p; setp.ne.s32 p, %2, 0; @p mov.f32 %0, %1; }" : "+f"(d) : "f"(s), "r"((int)c)); }
__device__ __forceinline__ float tanh_fast(float x) { float y; asm("tanh.approx.f32 %0, %1;" : "=f"(y) : "f"(x)); return y; }
__device__ __forceinline__ float gelu_half(float hx) {
  const float u = hx * fmaf(hx * hx, 8.f * 0.044715f * 0.7978845608028654f, 2.f * 0.7978845608028654f);
  return fmaf(hx, tanh_fast(u), hx);
}
__device__ __forceinline__ float4 lds128(uint32_t a) { float4 v; asm volatile("ld.shared.v4.f32 {%0,%1,%2,%3}, [%4];" : "=f"(v.x), "=f"(v.y), "=f"(v.z), "=f"(v.w) : "r"(a)); return v; }
__device__ __forceinline__ uint4 lds128u(uint32_t a) { uint4 v; asm volatile("ld.shared.v4.u32 {%0,%1,%2,%3}, [%4];" : "=r"(v.x), "=r"(v.y), "=r"(v.z), "=r"(v.w) : "r"(a) : "memory"); return v; }
__device__ __forceinline__ void stsm_x4_t(uint32_t a, uint32_t r0, uint32_t r1, uint32_t r2, uint32_t r3) {
  asm volatile("stmatrix.sync.aligned.m8n8.x4.trans.shared.b16 [%0], {%1,%2,%3,%4};" ::"r"(a), "r"(r0), "r"(r1), "r"(r2), "r"(r3) : "memory");
}
__device__ __forceinline__ void ldsm_x4_t(uint32_t a, uint32_t (&r)[4]) {
  asm volatile("ldmatrix.sync.aligned.m8n8.x4.trans.shared.b16 {%0,%1,%2,%3}, [%4];" : "=r"(r[0]), "=r"(r[1]), "=r"(r[2]), "=r"(r[3]) : "r"(a) : "memory");
}
__device__ __forceinline__ uint32_t movm_t(uint32_t v) { uint32_t r; asm volatile("movmatrix.sync.aligned.m8n8.trans.b16 %0, %1;" : "=r"(r) : "r"(v)); return r; }

__device__ __forceinline__ void mma_x_first(float (&d)[68], uint64_t da, uint64_t db) {
  asm volatile("wgmma.mma_async.sync.aligned.m64n136k16.f32.bf16.bf16 {%0,%1,%2,%3,%4,%5,%6,%7,%8,%9,%10,%11,%12,%13,%14,%15,%16,%17,%18,%19,%20,%21,%22,%23,%24,%25,%26,%27,%28,%29,%30,%31,%32,%33,%34,%35,%36,%37,%38,%39,%40,%41,%42,%43,%44,%45,%46,%47,%48,%49,%50,%51,%52,%53,%54,%55,%56,%57,%58,%59,%60,%61,%62,%63,%64,%65,%66,%67}, %68, %69, 0, 1, 1, 1, 0;" : "=f"(d[0]), "=f"(d[1]), "=f"(d[2]), "=f"(d[3]), "=f"(d[4]), "=f"(d[5]), "=f"(d[6]), "=f"(d[7]), "=f"(d[8]), "=f"(d[9]), "=f"(d[10]), "=f"(d[11]), "=f"(d[12]), "=f"(d[13]), "=f"(d[14]), "=f"(d[15]), "=f"(d[16]), "=f"(d[17]), "=f"(d[18]), "=f"(d[19]), "=f"(d[20]), "=f"(d[21]), "=f"(d[22]), "=f"(d[23]), "=f"(d[24]), "=f"(d[25]), "=f"(d[26]), "=f"(d[27]), "=f"(d[28]), "=f"(d[29]), "=f"(d[30]), "=f"(d[31]), "=f"(d[32]), "=f"(d[33]), "=f"(d[34]), "=f"(d[35]), "=f"(d[36]), "=f"(d[37]), "=f"(d[38]), "=f"(d[39]), "=f"(d[40]), "=f"(d[41]), "=f"(d[42]), "=f"(d[43]), "=f"(d[44]), "=f"(d[45]), "=f"(d[46]), "=f"(d[47]), "=f"(d[48]), "=f"(d[49]), "=f"(d[50]), "=f"(d[51]), "=f"(d[52]), "=f"(d[53]), "=f"(d[54]), "=f"(d[55]), "=f"(d[56]), "=f"(d[57]), "=f"(d[58]), "=f"(d[59]), "=f"(d[60]), "=f"(d[61]), "=f"(d[62]), "=f"(d[63]), "=f"(d[64]), "=f"(d[65]), "=f"(d[66]), "=f"(d[67]) : "l"(da), "l"(db));
}
template <int KB, int KK> __device__ __forceinline__ void mma_x(float (&d)[68], uint64_t da, uint64_t db) {
  if constexpr (KB == 0 && KK == 0) { mma_x_first(d, da, db); return; }
  asm volatile("{ .reg .b64 a, b; add.u64 a, %68, %70; add.u64 b, %69, %71;\n"
               "wgmma.mma_async.sync.aligned.m64n136k16.f32.bf16.bf16 {%0,%1,%2,%3,%4,%5,%6,%7,%8,%9,%10,%11,%12,%13,%14,%15,%16,%17,%18,%19,%20,%21,%22,%23,%24,%25,%26,%27,%28,%29,%30,%31,%32,%33,%34,%35,%36,%37,%38,%39,%40,%41,%42,%43,%44,%45,%46,%47,%48,%49,%50,%51,%52,%53,%54,%55,%56,%57,%58,%59,%60,%61,%62,%63,%64,%65,%66,%67}, a, b, 1, 1, 1, 1, 0; }"
               : "+f"(d[0]), "+f"(d[1]), "+f"(d[2]), "+f"(d[3]), "+f"(d[4]), "+f"(d[5]), "+f"(d[6]), "+f"(d[7]), "+f"(d[8]), "+f"(d[9]), "+f"(d[10]), "+f"(d[11]), "+f"(d[12]), "+f"(d[13]), "+f"(d[14]), "+f"(d[15]), "+f"(d[16]), "+f"(d[17]), "+f"(d[18]), "+f"(d[19]), "+f"(d[20]), "+f"(d[21]), "+f"(d[22]), "+f"(d[23]), "+f"(d[24]), "+f"(d[25]), "+f"(d[26]), "+f"(d[27]), "+f"(d[28]), "+f"(d[29]), "+f"(d[30]), "+f"(d[31]), "+f"(d[32]), "+f"(d[33]), "+f"(d[34]), "+f"(d[35]), "+f"(d[36]), "+f"(d[37]), "+f"(d[38]), "+f"(d[39]), "+f"(d[40]), "+f"(d[41]), "+f"(d[42]), "+f"(d[43]), "+f"(d[44]), "+f"(d[45]), "+f"(d[46]), "+f"(d[47]), "+f"(d[48]), "+f"(d[49]), "+f"(d[50]), "+f"(d[51]), "+f"(d[52]), "+f"(d[53]), "+f"(d[54]), "+f"(d[55]), "+f"(d[56]), "+f"(d[57]), "+f"(d[58]), "+f"(d[59]), "+f"(d[60]), "+f"(d[61]), "+f"(d[62]), "+f"(d[63]), "+f"(d[64]), "+f"(d[65]), "+f"(d[66]), "+f"(d[67])
               : "l"(da), "l"(db), "n"(KB * 512 + KK * 64), "n"(KB * (XP / 16) + KK * 2));
}
template <int KB, int KK> __device__ __forceinline__ void mma_h(float (&d)[68], uint64_t da, uint64_t db) {
  asm volatile("{ .reg .b64 a, b; add.u64 a, %64, %66; add.u64 b, %65, %67;\n"
               "wgmma.mma_async.sync.aligned.m64n128k16.f32.bf16.bf16 {%0,%1,%2,%3,%4,%5,%6,%7,%8,%9,%10,%11,%12,%13,%14,%15,%16,%17,%18,%19,%20,%21,%22,%23,%24,%25,%26,%27,%28,%29,%30,%31,%32,%33,%34,%35,%36,%37,%38,%39,%40,%41,%42,%43,%44,%45,%46,%47,%48,%49,%50,%51,%52,%53,%54,%55,%56,%57,%58,%59,%60,%61,%62,%63}, a, b, 1, 1, 1, 1, 1; }"
               : "+f"(d[0]), "+f"(d[1]), "+f"(d[2]), "+f"(d[3]), "+f"(d[4]), "+f"(d[5]), "+f"(d[6]), "+f"(d[7]), "+f"(d[8]), "+f"(d[9]), "+f"(d[10]), "+f"(d[11]), "+f"(d[12]), "+f"(d[13]), "+f"(d[14]), "+f"(d[15]), "+f"(d[16]), "+f"(d[17]), "+f"(d[18]), "+f"(d[19]), "+f"(d[20]), "+f"(d[21]), "+f"(d[22]), "+f"(d[23]), "+f"(d[24]), "+f"(d[25]), "+f"(d[26]), "+f"(d[27]), "+f"(d[28]), "+f"(d[29]), "+f"(d[30]), "+f"(d[31]), "+f"(d[32]), "+f"(d[33]), "+f"(d[34]), "+f"(d[35]), "+f"(d[36]), "+f"(d[37]), "+f"(d[38]), "+f"(d[39]), "+f"(d[40]), "+f"(d[41]), "+f"(d[42]), "+f"(d[43]), "+f"(d[44]), "+f"(d[45]), "+f"(d[46]), "+f"(d[47]), "+f"(d[48]), "+f"(d[49]), "+f"(d[50]), "+f"(d[51]), "+f"(d[52]), "+f"(d[53]), "+f"(d[54]), "+f"(d[55]), "+f"(d[56]), "+f"(d[57]), "+f"(d[58]), "+f"(d[59]), "+f"(d[60]), "+f"(d[61]), "+f"(d[62]), "+f"(d[63])
               : "l"(da), "l"(db), "n"(KB * 512 + KK * 128), "n"(KB * (XP / 16) + KK * 256));
}
template <int OFF> __device__ __forceinline__ void mma_qk(float (&d)[32], const uint32_t (&a)[4], uint64_t db, int one) {
  asm volatile("{ .reg .pred p; .reg .b64 b; add.u64 b, %36, %37; setp.eq.s32 p, %38, 0;\n"
               "wgmma.mma_async.sync.aligned.m64n64k16.f32.bf16.bf16 {%0,%1,%2,%3,%4,%5,%6,%7,%8,%9,%10,%11,%12,%13,%14,%15,%16,%17,%18,%19,%20,%21,%22,%23,%24,%25,%26,%27,%28,%29,%30,%31}, {%32,%33,%34,%35}, b, p, 1, 1, 1; }"
               : "+f"(d[0]), "+f"(d[1]), "+f"(d[2]), "+f"(d[3]), "+f"(d[4]), "+f"(d[5]), "+f"(d[6]), "+f"(d[7]), "+f"(d[8]), "+f"(d[9]), "+f"(d[10]), "+f"(d[11]), "+f"(d[12]), "+f"(d[13]), "+f"(d[14]), "+f"(d[15]), "+f"(d[16]), "+f"(d[17]), "+f"(d[18]), "+f"(d[19]), "+f"(d[20]), "+f"(d[21]), "+f"(d[22]), "+f"(d[23]), "+f"(d[24]), "+f"(d[25]), "+f"(d[26]), "+f"(d[27]), "+f"(d[28]), "+f"(d[29]), "+f"(d[30]), "+f"(d[31])
               : "r"(a[0]), "r"(a[1]), "r"(a[2]), "r"(a[3]), "l"(db), "n"(OFF), "r"(one));
}
template <int OFF, int ACC> __device__ __forceinline__ void mma_pv(float (&d)[12], const uint32_t* a, uint64_t db) {
  asm volatile("{ .reg .b64 b; add.u64 b, %16, %17;\n"
               "wgmma.mma_async.sync.aligned.m64n24k16.f32.bf16.bf16 {%0,%1,%2,%3,%4,%5,%6,%7,%8,%9,%10,%11}, {%12,%13,%14,%15}, b, %18, 1, 1, 0; }"
               : "+f"(d[0]), "+f"(d[1]), "+f"(d[2]), "+f"(d[3]), "+f"(d[4]), "+f"(d[5]), "+f"(d[6]), "+f"(d[7]), "+f"(d[8]), "+f"(d[9]), "+f"(d[10]), "+f"(d[11])
               : "r"(a[0]), "r"(a[1]), "r"(a[2]), "r"(a[3]), "l"(db), "n"(OFF), "n"(ACC));
}
__device__ __forceinline__ uint64_t desc64(uint32_t lo, uint32_t hi, int lane) {
  return ((uint64_t)__shfl_sync(0xffffffffu, hi + (lane >> 4), 0) << 32) | __shfl_sync(0xffffffffu, lo + (lane >> 4), 0);
}

constexpr float QSCALE = 0.25f * 1.4426950408889634f;

__device__ __forceinline__ void attn_exact(const unsigned char* kh, int row0, float (&out)[8]) {
  const int q = threadIdx.x & 3;
  const unsigned char* vh = kh + 65536;
  auto elem = [&](const unsigned char* base, int j, int d) {
    return __uint_as_float((uint32_t)__ldcg((const unsigned short*)(base + (d >> 3) * 32768 + (j >> 3) * 128 + (d & 7) * 16 + (j & 7) * 2)) << 16);
  };
#pragma unroll
  for (int i = 0; i < 8; i++) out[i] = 0.f;
#pragma unroll 1
  for (int hf = 0; hf < 2; hf++) {
    const int row = row0 + hf * 8, j0 = max(row - 255, 0);
    float qv[16];
#pragma unroll
    for (int d = 0; d < 16; d++) qv[d] = elem(kh + 131072, row, d);
    auto score = [&](int j) {
      float sc = 0.f;
#pragma unroll
      for (int d = 0; d < 16; d++) sc = fmaf(qv[d], elem(kh, j, d), sc);
      return sc;
    };
    float m = -INFINITY;
#pragma unroll 1
    for (int j = j0 + q; j <= row; j += 4) m = fmaxf(m, score(j));
    __syncwarp();
    m = fmaxf(m, __shfl_xor_sync(0xffffffffu, m, 1)); m = fmaxf(m, __shfl_xor_sync(0xffffffffu, m, 2));
    float l = 0.f, o[16];
#pragma unroll
    for (int d = 0; d < 16; d++) o[d] = 0.f;
#pragma unroll 1
    for (int j = j0 + q; j <= row; j += 4) {
      const float pj = ex2(score(j) - m);
      l += pj;
#pragma unroll
      for (int d = 0; d < 16; d++) o[d] = fmaf(pj, elem(vh, j, d), o[d]);
    }
    __syncwarp();
    l += __shfl_xor_sync(0xffffffffu, l, 1); l += __shfl_xor_sync(0xffffffffu, l, 2);
#pragma unroll
    for (int d = 0; d < 16; d++) { o[d] += __shfl_xor_sync(0xffffffffu, o[d], 1); o[d] += __shfl_xor_sync(0xffffffffu, o[d], 2); }
    const float inv = 1.f / l;
#pragma unroll
    for (int i = 0; i < 4; i++) {
      if (q == i && hf == 0) { out[0] = o[2 * i] * inv; out[1] = o[2 * i + 1] * inv; out[4] = o[8 + 2 * i] * inv; out[5] = o[9 + 2 * i] * inv; }
      if (q == i && hf == 1) { out[2] = o[2 * i] * inv; out[3] = o[2 * i + 1] * inv; out[6] = o[8 + 2 * i] * inv; out[7] = o[9 + 2 * i] * inv; }
    }
  }
}

template <int N> struct IC { static constexpr int value = N; };
struct Params {
  const __nv_bfloat16* x;
  const __nv_bfloat16* wqkv;
  const __nv_bfloat16* wo;
  const __nv_bfloat16* w1;
  const __nv_bfloat16* b1;
  const __nv_bfloat16* w2;
  const __nv_bfloat16* b2;
  int one;
};

__global__ void __launch_bounds__(NTHREADS, 1)
fused_kernel(const __grid_constant__ CUtensorMap map_x, const __grid_constant__ CUtensorMap map_wqkv,
             const __grid_constant__ CUtensorMap map_w1, const __grid_constant__ CUtensorMap map_w2,
             const __grid_constant__ CUtensorMap map_w2s, const __grid_constant__ CUtensorMap map_wo,
             const __grid_constant__ CUtensorMap map_out, const Params p) {
  extern __shared__ __align__(1024) unsigned char smem_raw[];
  const uint32_t sb = __shfl_sync(0xffffffffu, smem_u32(smem_raw), 0);
  const uint32_t bar0 = sb + OFF_BAR;
  auto BAR = [&](int i) { return bar0 + 8u * i; };
  const int tid = threadIdx.x, warp =
    __shfl_sync(0xffffffffu, tid >> 5, 0), lane = tid & 31;
  if (threadIdx.x == 0) { prefetch_map(&map_x); prefetch_map(&map_wqkv); }
  const int bid = blockIdx.x;
  const int cl = bid >> 1;
  const int gp = cl < 4 ? 0 : (cl < 36 ? 1 + ((cl - 4) & 7) : 9 + (cl - 36) % 7);
  const int gi = cl < 4 ? cl : (cl < 36 ? (cl - 4) >> 3 : (cl - 36) / 7);
  const int r = gp, g = gi * 2 + (bid & 1);
  const int cta = r * 8 + g;

  auto wmap = [&](int t) { return t < 3 ? &map_wqkv : &map_w1; };
  auto wcol = [&](int t) { return t < 2 ? 512 + g * 64 + t * 32 : (t == 2 ? g * 64 : g * 176 + (t - 3) * 64); };
  auto wload = [&](const CUtensorMap* m, int c0, int c1, int kb, uint32_t bar) {
    tma2d(sb + OFF_W + kb * 8192, m, c0, kb * 64, bar);
    tma2d(sb + OFF_W + kb * 8192 + 4096, m, c1, kb * 64, bar);
  };
  if (warp == 4) {
   const bool lead = elect_one();
   if (lead) {
#pragma unroll
    for (int i = 0; i < 8; i++) mbar_init(BAR(B_AF + i), 1);
    fence_proxy_smem();
    mbar_expect_tx(BAR(B_AF), 24576);
    tma2d(sb + OFF_X, &map_x, 0, r * 128, BAR(B_AF));
    wload(wmap(ORDER & 15), wcol(ORDER & 15), wcol(ORDER & 15) + ((ORDER & 15) < 2 ? 512 : 32), 0, BAR(B_AF));
   }
   __syncwarp();
   nb_arrive(0, NTHREADS);
   cluster_arrive();
   if (elect_one()) {
#pragma unroll
    for (int n = 1; n < 8; n++) {
      mbar_expect_tx(BAR(B_AF + n), 24576);
      tma2d(sb + OFF_X + n * XP, &map_x, n * 64, r * 128, BAR(B_AF + n));
      wload(wmap(ORDER & 15), wcol(ORDER & 15), wcol(ORDER & 15) + ((ORDER & 15) < 2 ? 512 : 32), n, BAR(B_AF + n));
    }
   }
   __syncwarp();
  }
  if (warp >= 16) {
   asm volatile("setmaxnreg.dec.sync.aligned.u32 32;");
  if (warp == 16) {
    if (elect_one()) {
#pragma unroll
      for (int i = 0; i < 28; i++) mbar_init(BAR(B_HT + i), 1);
    }
    __syncwarp();
    cluster_arrive();
    nb_sync(0, NTHREADS);
  } else {
    if (elect_one()) {
      if (warp == 17) {
#pragma unroll
        for (int i = 0; i < 8; i++) { mbar_init(BAR(B_WF + i), 1); mbar_init(BAR(B_WE + i), 4); }
        if ((sb & 0x3FFFF) != SB0) __trap();
      } else if (warp == 18) {
#pragma unroll
        for (int i = 0; i < 9; i++) mbar_init(BAR(B_PUB + i), i < 5 ? 4 : 8);

#pragma unroll
        for (int i = 0; i < 4; i++) mbar_init(BAR(B_SLOT + i), 1);
        mbar_init(BAR(B_XINIT), 1);
        mbar_init(BAR(B_STAT), 3);
        mbar_expect_tx(BAR(B_STAT), 2048);
      } else {
#pragma unroll
        for (int i = 0; i < 8; i++) { mbar_init(BAR(B_ATT + i), (i & 4) ? 8 : 1); if (i < 6) mbar_init(BAR(B_KV0 + i), 1); if (i < 2) mbar_init(BAR(B_GRP + i), 8); }
      }
      asm volatile("fence.mbarrier_init.release.cluster;" ::: "memory");
      fence_proxy_smem();
    }
    __syncwarp();
    cluster_arrive();
    nb_sync(0, NTHREADS);
  }

   if (warp == 16) {
    if (elect_one()) {
#pragma unroll 1
      for (int task = 1; task < 6; task++) {
        const int t = (ORDER >> (4 * task)) & 15, c0 = wcol(t), c1 = c0 + (t < 2 ? 512 : 32);
        const CUtensorMap* m = wmap(t);
        const uint32_t par = (task & 1) ^ 1;
#pragma unroll
        for (int kb = 0; kb < 8; kb++) {
          mbar_wait(BAR(B_WE + kb), par);
          mbar_expect_tx(BAR(B_WF + kb), 8192);
          wload(m, c0, c1, kb, BAR(B_WF + kb));
        }
      }
#pragma unroll 1
      for (int blk = 0; blk < 3; blk++) {
        const uint32_t par = (blk & 1) ^ 1, tbytes = blk == 2 ? 12288 : 16384;
        const unsigned char* src = g_h + (uint32_t)(r * 24 + blk) * 16384;
        const uint32_t hb = BAR(B_HT + blk * 8);
        const CUtensorMap* m = blk == 2 ? &map_w2s : &map_w2;
#pragma unroll
        for (int kb = 0; kb < 8; kb++) {
          mbar_wait(BAR(B_WE + kb), par);
          if (DEPTH < 8) mbar_wait(BAR(B_AF + ((kb - DEPTH) & 7)), kb >= DEPTH ? par : par ^ 1);
          mbar_expect_tx(BAR(B_AF + kb), tbytes + tbytes / 2);
          tma2d(sb + OFF_W + kb * 8192, m, g * 64, blk * 64 + kb * 176, BAR(B_AF + kb));
          mbar_wait(hb + kb * 8, 0);
          bulk_ld(sb + OFF_X + kb * XP, src + kb * 49152, tbytes, BAR(B_AF + kb));
        }
      }
#pragma unroll
      for (int kb = 0; kb < 8; kb++) {
        mbar_wait(BAR(B_WE + kb), 0);
        if (DEPTH < 8 && kb < 4) mbar_wait(BAR(B_AF + ((kb - DEPTH) & 7)), kb >= DEPTH ? 0 : 1);
        if (kb < 4) mbar_expect_tx(BAR(B_AF + kb), 24576); else mbar_expect_only(BAR(B_AF + kb), 8192);
        tma3d(sb + OFF_W + kb * 8192, &map_wo, g * 64, (kb >> 1) * 16, (kb & 1) * 4, BAR(B_AF + kb));
        if (kb < 4) {
          if (!(kb & 1)) mbar_wait(BAR(B_GRP + (kb >> 1)), 0);
          bulk_ld(sb + OFF_X + kb * XP, g_o + (uint32_t)(r * 8 + kb) * 16384, 16384, BAR(B_AF + kb));
        }
        if (kb >= 4) mbar_arrive(BAR(B_SLOT + kb - 4));
      }
      mbar_wait(BAR(B_WE), 1);
      mbar_expect_tx(BAR(B_XINIT), 16384);
      tma2d(sb + OFF_X, &map_x, g * 64, r * 128, BAR(B_XINIT));
    }
   } else if (warp == 17) {
    {
      unsigned char* kv0 = g_kv + (uint32_t)(g * 12) * 65536 + (uint32_t)r * 2048 + lane * 16;
#pragma unroll
      for (int i = 0; i < 16; i++) *(uint4*)(kv0 + (i >> 2) * 32768 + (i & 3) * 512) = make_uint4(0, 0, 0, 0);
      __syncwarp();
    }
    if (lane == 0) {
      const uint32_t tag = ld_relaxed(&g_epoch[cta * 32]) * 2 + 1;
      uint32_t* fl = &g_flags[cta * 32];
      fence_gpu();
      st_relaxed(fl + 8, tag);
      mbar_arrive(BAR(B_STAT));
#pragma unroll 1
      for (int n = 0; n < NPUB; n++) {
        const int i = (PUBORD >> (4 * n)) & 15;
        mbar_wait_sleep(BAR(B_PUB + i), 0);
        fence_gpu();
        st_relaxed(fl + i, tag);
        if (n == 0) {
          l2_prefetch((const unsigned char*)p.w2 + (size_t)cta * 11008, 11008);
          l2_prefetch((const unsigned char*)p.wo + (size_t)cta * 4096, 4096);
        }
      }
    }
   } else if (warp == 18) {
    const uint32_t tag = ld_relaxed(&g_epoch[cta * 32]) * 2 + 1;
    const uint32_t* fp = &g_flags[(r * 8 + (lane & 7)) * 32];
    if (lane == 0) {
      mbar_wait_sleep(BAR(B_AF + PFAT), 0);
      l2_prefetch((const unsigned char*)p.wqkv + (size_t)cta * 12288, 12288);
      l2_prefetch((const unsigned char*)p.w1 + (size_t)cta * 11008, 11008);
      prefetch_map(&map_w1); prefetch_map(&map_wqkv); prefetch_map(&map_w2); prefetch_map(&map_w2s); prefetch_map(&map_wo); prefetch_map(&map_out);
    }
    __syncwarp();
    mbar_wait_sleep(BAR(B_PUB + 2), 0);
    int ev = 2 + (lane >> 3);
    const int evend = lane < 24 ? ev + 1 : 7;
#pragma unroll 1
    for (int n = 0; n < SPIN_LIMIT && __any_sync(0xffffffffu, ev < evend); n++) {
      if (ev < evend && ld_acquire(fp + ev) == tag) {
        fence_proxy_global();
        mbar_arrive(BAR(lane < 24 ? B_HT + lane : B_GRP + ev - 5));
        ev++;
      }
      __syncwarp();
    }
   } else {
    const uint32_t tag = ld_relaxed(&g_epoch[cta * 32]) * 2 + 1;
    {
      uint32_t bv[4];
#pragma unroll
      for (int i = 0; i < 3; i++) { const int f = g * 176 + i * 64 + lane * 2; bv[i] = f < 1376 ? __ldg((const uint32_t*)(p.b1 + f)) : 0u; }
      bv[3] = __ldg((const uint32_t*)(p.b2 + g * 64 + lane * 2));
#pragma unroll
      for (int i = 0; i < 4; i++) sts32u(sb + OFF_BIAS + i * XP + lane * 4, bv[i]);
      sts32u(sb + OFF_BIAS + 4 * XP + lane * 4, tag);
      __syncwarp();
      mbar_arrive_warp(BAR(B_STAT));
    }
    const unsigned char* src = g_kv + (uint32_t)(g * 12) * 65536 + (uint32_t)r * 2048;
    const uint32_t kv = sb + OFF_KV, bytesA = r >= 2 ? 8192 : 4096, bytesB = r >= 1 ? 4096 : 0;
    auto loadA = [&](auto V) {
      constexpr int v = V.value;
      const uint32_t full = BAR(B_ATT + 2 * v);
      mbar_expect_tx(full, bytesA);
      bulk_ld(kv + (v ? KV_V0 : KV_K0), src + v * 65536, 2048, full);
      bulk_ld(kv + (v ? KV_V0 : KV_K0) + 2048, src + v * 65536 + 32768, 2048, full);
      if (r >= 2) {
        bulk_ld(kv + (v ? KV_V2 : KV_K2), src + v * 65536 - 4096, 2048, full);
        bulk_ld(kv + (v ? KV_V2 + 8192 : KV_K2 + 2048), src + v * 65536 + 32768 - 4096, 2048, full);
      }
    };
    auto loadB = [&](auto V) {
      constexpr int v = V.value;
      const uint32_t full = BAR(B_ATT + 2 * v + 1);
      mbar_expect_tx(full, bytesB);
      if (r >= 1) {
        bulk_ld(kv + (v ? KV_V1 : KV_K1), src + v * 65536 - 2048, 2048, full);
        bulk_ld(kv + (v ? KV_V1 + 6144 : KV_K1 + 4096), src + v * 65536 + 32768 - 2048, 2048, full);
      }
    };
    const int nb = lane & 3;
    const bool act = lane < 8 && nb < 3 && r - nb >= 0;
    const uint32_t* fp = &g_flags[((act ? r - nb : r) * 8 + g) * 32 + (lane >> 2 & 1)];
    uint32_t seen = 0;
    auto poll = [&](uint32_t need) {
#pragma unroll 1
      for (int n = 0; n < SPIN_LIMIT && (seen & need) != need; n++) { seen = __ballot_sync(0xffffffffu, !act || ld_acquire(fp) == tag); __nanosleep(100); }
      fence_proxy_global();
    };
    if (lane < 4) mbar_arrive(BAR(B_ATT + lane));
    mbar_wait_sleep(BAR(B_PUB), 0);
#pragma unroll 1
    for (int h = 1; h < 4; h++) {
      const uint32_t par = (h & 1) ^ 1;
      src += 196608;
      if (h < 3) poll(h == 1 ? 0x0f : 0xf0);
      mbar_wait_sleep(BAR(B_ATT + 4), par);
      if (elect_one()) loadA(IC<0>());
      __syncwarp();
      mbar_wait_sleep(BAR(B_ATT + 6), par);
      if (elect_one()) loadA(IC<1>());
      __syncwarp();
      mbar_wait_sleep(BAR(B_ATT + 5), par);
      if (elect_one()) loadB(IC<0>());
      __syncwarp();
      mbar_wait_sleep(BAR(B_ATT + 7), par);
      if (elect_one()) loadB(IC<1>());
      __syncwarp();
    }
   }
  } else if (warp < 8) {
    if (warp != 4) cluster_arrive();
    const int wg = warp >> 2, w = warp & 3, q = lane & 3;
    float acc[68];
    const uint64_t dWx = desc64(desc_lo(OFF_W, 4096), HI_SW64, lane), dX = desc64(desc_lo(OFF_X, 16), HI_SW128, lane);
    {
      if (wg == 0) {
        if (r < 2) {
#pragma unroll
          for (int i = 0; i < 6; i++) sts128u(sb + OFF_KV + i * 2048 + tid * 16, 0, 0, 0, 0);
          sts128u(sb + OFF_KV + KV_K2 + tid * 16, 0, 0, 0, 0);
          sts128u(sb + OFF_KV + KV_K2 + 2048 + tid * 16, 0, 0, 0, 0);
        }
        const uint32_t ones = 0x3f803f80u;
        if (tid < 64) sts128u(sb + OFF_X + (tid >> 3) * XP + 16384 + (tid & 7) * 16, ones, ones, ones, ones);
        sts128u(sb + OFF_KV + KV_ONES + tid * 16, ones, ones, ones, ones);
        fence_proxy_smem();
      }
    }
    if (warp != 4) nb_sync(0, NTHREADS);
#pragma unroll 1
    for (int pos = wg; pos < 6; pos += 2) {
      const int t = (ORDER >> (4 * pos)) & 15;
      if (pos > 0) nb_sync(NB_ORD + (wg ^ 1), 256);
      uint32_t fbar = BAR(pos == 0 ? B_AF : B_WF), fpar = pos == 0 ? 0 : wg ^ 1;
      asm volatile("" : "+r"(fbar), "+r"(fpar));
      auto stage = [&](auto KB) {
        constexpr int kb = KB.value;
        wg_fence();
        mma_x<kb, 0>(acc, dWx, dX); mma_x<kb, 1>(acc, dWx, dX);
        wg_commit();
        wg_wait<1>();
        wg_fence();
        mma_x<kb, 2>(acc, dWx, dX); mma_x<kb, 3>(acc, dWx, dX);
        wg_commit();
        if (kb > 0) mbar_arrive_warp(BAR(B_WE + kb - 1));
        if (kb < 7) mbar_wait(fbar + (kb + 1) * 8, fpar);
        else if (pos < 5) nb_arrive(NB_ORD + wg, 256);
        wg_wait<1>();
      };
      mbar_wait(fbar, fpar);
      stage(IC<0>()); stage(IC<1>()); stage(IC<2>()); stage(IC<3>()); stage(IC<4>()); stage(IC<5>()); stage(IC<6>()); stage(IC<7>());
      wg_wait<0>();
      pin(acc);
      mbar_arrive_warp(BAR(B_WE + 7));
      if (pos < 2) mbar_wait(BAR(B_STAT), 0);
      const uint32_t sta = sb + OFF_ST + (t < 3 ? 0 : 4 * XP) + q * 16;
      float4 st[PF];
#pragma unroll
      for (int j = 0; j < PF; j++) st[j] = lds128(sta + (j >> 2) * XP + (j & 3) * 64);
      auto stat = [&](int j) {
        const float4 s = st[j % PF];
        if (j + PF < 16) st[j % PF] = lds128(sta + ((j + PF) >> 2) * XP + ((j + PF) & 3) * 64);
        return s;
      };
      const float c0 = __shfl_sync(0xffffffffu, acc[64], lane & ~3), c1 = __shfl_sync(0xffffffffu, acc[66], lane & ~3);
      if (t < 2) {
        uint32_t* dst = (uint32_t*)(g_kv + (uint32_t)((g * 4 + t * 2 + (w & 1)) * 3 + (w >> 1)) * 65536 + (uint32_t)r * 2048) + lane;
#pragma unroll
        for (int j = 0; j < 16; j++) {
          const float4 s = stat(j);
          dst[j * 32] = nonzero(pack_bf16(s.z * fmaf(s.x, c0, acc[4 * j]), s.w * fmaf(s.y, c0, acc[4 * j + 1])));
          dst[j * 32 + 8192] = nonzero(pack_bf16(s.z * fmaf(s.x, c1, acc[4 * j + 2]), s.w * fmaf(s.y, c1, acc[4 * j + 3])));
        }
        __syncwarp();
        mbar_arrive_warp(BAR(B_PUB + t));
      } else if (t == 2) {
        uint32_t* dst = (uint32_t*)(g_kv + (uint32_t)((g * 4 + w) * 3 + 2) * 65536 + (uint32_t)r * 2048) + lane;
        uint32_t pk[32];
#pragma unroll
        for (int j = 0; j < 16; j++) {
          float4 s = stat(j);
          s.z *= QSCALE; s.w *= QSCALE;
          pk[2 * j] = pack_bf16(s.z * fmaf(s.x, c0, acc[4 * j]), s.w * fmaf(s.y, c0, acc[4 * j + 1]));
          pk[2 * j + 1] = pack_bf16(s.z * fmaf(s.x, c1, acc[4 * j + 2]), s.w * fmaf(s.y, c1, acc[4 * j + 3]));
          dst[j * 32] = pk[2 * j];
          dst[j * 32 + 8192] = pk[2 * j + 1];
        }
        if (w == 0) {
#pragma unroll
          for (int sl = 0; sl < 8; sl++) sts128u(sb + OFF_Q0 + sl * XP + lane * 16, pk[4 * sl], pk[4 * sl + 2], pk[4 * sl + 1], pk[4 * sl + 3]);
        }
        nb_arrive(NB_Q, 384);
      } else {
        if (t < 5 || w < 3) {
          const uint32_t ba = sb + OFF_BIAS + (t - 3) * XP + w * 32 + (lane >> 2) * 2;
          const float bias0 = 0.5f * lds_bf16(ba), bias1 = 0.5f * lds_bf16(ba + 16);
          uint32_t* dst = (uint32_t*)(g_h + (uint32_t)(cta * 3 + t - 3) * 16384 + (uint32_t)w * 4096) + lane;
#pragma unroll
          for (int j = 0; j < 16; j++) {
            const float4 s = stat(j);
            dst[j * 32] = pack_bf16(gelu_half(fmaf(fmaf(s.x, c0, acc[4 * j]), s.z, bias0)), gelu_half(fmaf(fmaf(s.y, c0, acc[4 * j + 1]), s.w, bias0)));
            dst[j * 32 + 512] = pack_bf16(gelu_half(fmaf(fmaf(s.x, c1, acc[4 * j + 2]), s.z, bias1)), gelu_half(fmaf(fmaf(s.y, c1, acc[4 * j + 3]), s.w, bias1)));
          }
        }
        if (pos == 5) nb_arrive(NB_ORD + 1, 256);
        if (pos < 5) {
          __syncwarp();
          mbar_arrive_warp(BAR(B_PUB + 2 + t - 3));
        } else {
          const uint32_t tag = lds32u(sb + OFF_BIAS + 4 * XP);
          nb_sync(3, 128);
          if (tid == 128) { fence_gpu(); st_relaxed(&g_flags[cta * 32 + 4], tag); }
        }
      }
    }
    {
      if (wg == 0) {
        const uint32_t moff = ((lane >> 4) * 8 + (lane & 7)) * 128 + (((w * 2 + ((lane >> 3) & 1)) ^ (lane & 7)) << 4);
        {
          const uint32_t ba = sb + OFF_BIAS + 3 * XP + w * 32 + (lane >> 2) * 2;
          const float b0 = lds_bf16(ba), b1 = lds_bf16(ba + 16);
#pragma unroll
          for (int i = 0; i < 64; i++) acc[i] = (i & 2) ? b1 : b0;
          pin(acc);
        }
        nb_sync(NB_ORD + 1, 256);
        mbar_wait(BAR(B_AF), 1);
        const uint64_t dWh = desc64(desc_lo(OFF_W, 8192), HI_SW128, lane), dH = desc64(desc_lo(OFF_X, 2048), 8, lane);
#pragma unroll 1
        for (int grp = 0; grp < 4; grp++) {
          uint32_t fpar = (grp & 1) ^ 1;
          asm volatile("" : "+r"(fpar));
          auto stage = [&](auto KB) {
            constexpr int kb = KB.value;
            if (grp != 2) { wg_fence(); mma_h<kb, 3>(acc, dWh, dH); wg_commit(); }
            wg_fence();
            mma_h<kb, 0>(acc, dWh, dH);
            wg_commit();
            wg_wait<1>();
            wg_fence();
            mma_h<kb, 1>(acc, dWh, dH); mma_h<kb, 2>(acc, dWh, dH);
            wg_commit();
            if (kb >= LAG) mbar_arrive_warp(BAR(B_WE + kb - LAG)); else mbar_arrive_warp_if(BAR(B_WE + kb + 8 - LAG), grp > 0);
            if (kb < 7) mbar_wait(BAR(B_AF + kb + 1), fpar);
            else if (grp < 3) mbar_wait(BAR(B_AF), fpar ^ 1);
            wg_wait<1>();
          };
          stage(IC<0>()); stage(IC<1>()); stage(IC<2>()); stage(IC<3>()); stage(IC<4>()); stage(IC<5>()); stage(IC<6>()); stage(IC<7>());
        }
        mbar_wait(BAR(B_XINIT), 0);
        uint32_t xv[4][4];
#pragma unroll
        for (int s = 0; s < 4; s++) ldsm_x4_t(sb + OFF_X + s * 2048 + moff, xv[s]);
        wg_wait<0>();
        pin(acc);
#pragma unroll
        for (int s = 0; s < 8; s++) {
          uint32_t o[4];
#pragma unroll
          for (int i = 0; i < 4; i++) o[i] = pack_bf16(acc[8 * s + 2 * i] + bf_lo(xv[s & 3][i]), acc[8 * s + 2 * i + 1] + bf_hi(xv[s & 3][i]));
          if (s < 4) ldsm_x4_t(sb + OFF_X + (s + 4) * 2048 + moff, xv[s]);
          stsm_x4_t(sb + OFF_X + s * 2048 + moff, o[0], o[1], o[2], o[3]);
          if (s == 3) {
            fence_proxy_smem();
            nb_sync(NB_OUT, 128);
            if (warp == 0 && elect_one()) tma2d_store(&map_out, g * 64, r * 128, sb + OFF_X);
          }
        }
        fence_proxy_smem();
        nb_sync(NB_OUT, 128);
        if (warp == 0 && elect_one()) {
          tma2d_store(&map_out, g * 64, r * 128 + 64, sb + OFF_X + 8192);
          asm volatile("cp.async.bulk.commit_group;" ::: "memory");
          atomicAdd(&g_epoch[cta * 32], 1u);
          asm volatile("cp.async.bulk.wait_group.read 0;" ::: "memory");
        }
      } else {
        const uint32_t bar = BAR(B_O3 + w), dst = sb + OFF_X + (4 + w) * XP;
        mbar_wait_sleep(BAR(B_SLOT + w), 0);
        if (!mbar_test(BAR(B_PUB + 7 + (w >> 1)), 0)) {
          mbar_wait(BAR(B_PUB + 7 + (w >> 1)), 0);
          __nanosleep(ODELAY);
        }
#pragma unroll 1
        for (int n = 0; n < SPIN_LIMIT; n++) {
          if (elect_one()) { mbar_expect_tx(bar, 16384); bulk_ld(dst, g_o + (r * 8 + 4 + w) * 16384, 16384, bar); }
          __syncwarp();
          mbar_wait(bar, n & 1);
          uint32_t ok = 1;
#pragma unroll
          for (int k = 0; k < 16; k++) ok = min(ok, lds32u(dst + k * 1024 + lane * 32 + (lane >> 2) * 4));
          if (__all_sync(0xffffffffu, ok != 0)) break;
          fence_proxy_smem();
        }
        mbar_arrive_warp(BAR(B_AF + 4 + w));
      }
    }
  } else {
    cluster_arrive();
    nb_sync(0, NTHREADS);
    asm volatile("setmaxnreg.inc.sync.aligned.u32 128;");
    const int at = tid - 256, aw = warp - 8, t = aw >> 2, w = aw & 3, q = lane & 3;
    {
      const int row = (g & 1) * 64 + (at >> 2), e = row >> 1;
      const uint32_t xa = sb + OFF_X + row * 128 + (((q * 2) ^ (row & 7)) << 4);
      const uint32_t sdst = mapa(sb + OFF_ST + ((lane & 2) * 2 + (e >> 4)) * XP + (e & 15) * 16, lane & 1), sbar = mapa(BAR(B_STAT), lane & 1);
      cluster_wait();
      float s4[4] = {0.f, 0.f, 0.f, 0.f}, q4[4] = {0.f, 0.f, 0.f, 0.f};
      uint4 v[8][2];
#pragma unroll
      for (int kb = 0; kb < 8 + SPF; kb++) {
        if (kb < 8) {
          mbar_wait(BAR(B_AF + kb), 0);
          v[kb][0] = lds128u(xa + kb * XP); v[kb][1] = lds128u((xa ^ 16) + kb * XP);
        }
        if (kb >= SPF) {
          const uint4 a = v[kb - SPF][0], b = v[kb - SPF][1];
          const uint32_t u[8] = {a.x, a.y, a.z, a.w, b.x, b.y, b.z, b.w};
#pragma unroll
          for (int i = 0; i < 8; i++) {
            const float d0 = bf_lo(u[i]), d1 = bf_hi(u[i]);
            s4[i & 1] += d0; s4[2 + (i & 1)] += d1; q4[i & 1] = fmaf(d0, d0, q4[i & 1]); q4[2 + (i & 1)] = fmaf(d1, d1, q4[2 + (i & 1)]);
          }
          pin(s4); pin(q4);
        }
      }
      float s0 = (s4[0] + s4[1]) + (s4[2] + s4[3]), q0 = (q4[0] + q4[1]) + (q4[2] + q4[3]);
      s0 += __shfl_xor_sync(0xffffffffu, s0, 1); q0 += __shfl_xor_sync(0xffffffffu, q0, 1);
      s0 += __shfl_xor_sync(0xffffffffu, s0, 2); q0 += __shfl_xor_sync(0xffffffffu, q0, 2);
      s0 *= 1.f / 512.f;
      const float var = fmaxf(fmaf(-s0, s0, q0 * (1.f / 512.f)), 0.f), nmean = -s0;
      const float rstd = rsqrt_fast(var + 1e-5f);
      const float sc = (lane & 2) ? 0.5f * rstd * rsqrt_fast(var * rstd * rstd + 1e-5f) : rstd;
      const float nm2 = __shfl_down_sync(0xffffffffu, nmean, 4), sc2 = __shfl_down_sync(0xffffffffu, sc, 4);
      if (!(lane & 4)) st_async4(sdst, make_float4(nmean, nm2, sc, sc2), sbar);
    }

    const uint32_t AB = BAR(B_ATT);
    uint32_t* odst = (uint32_t*)(g_o + (uint32_t)(r * 8 + (g >> 2)) * 16384 + (uint32_t)(g & 3) * 4096 + (uint32_t)(t * 8 + w * 2) * 128) + lane;
#pragma unroll
    for (int i = 0; i < 8; i++) st_relaxed(odst + (2 + (i >> 2)) * 8192 + (i & 1) * 32 + (i & 2) * 256, 0);
    const uint32_t* qp = (const uint32_t*)(g_kv + (uint32_t)(g * 12 + 2) * 65536 + (uint32_t)(r * 16 + aw * 2) * 128) + lane;
    float X[32], Y[32], O[12];
    uint32_t P[16], Q[4];
    uint4 Qraw;
    bool okA = false, okB = false;
    const bool pe0 = 2 * q <= (lane >> 2), pe1 = 2 * q + 1 <= (lane >> 2);
    const int onev = tid;
    const int tz = w * 16 + (lane >> 2) - 2 * q;
    const uint32_t dmask = pe1 ? 0xffffffffu : (pe0 ? 0x0000ffffu : 0u);
#pragma unroll
    for (int i = 0; i < 32; i++) { X[i] = 0.f; Y[i] = 0.f; }
#pragma unroll
    for (int i = 0; i < 16; i++) P[i] = 0;
#pragma unroll
    for (int i = 0; i < 12; i++) O[i] = 0.f;
    pin(O); pin(P); pin(X); pin(Y);

    auto exps = [&](float (&S)[32], auto I0, auto I1) {
#pragma unroll
      for (int i = I0.value; i < I1.value; i++) ex2_ip(S[i], onev);
      pin(S);
    };
    auto pk = [&](const float (&S)[32], int i, bool raw) { return raw ? pack_bf16(ex2(S[i]), ex2(S[i + 1])) : pack_bf16(S[i], S[i + 1]); };
    auto pack = [&](float (&S)[32], auto RAW) {
#pragma unroll
      for (int i = 0; i < 16; i++) P[i] = pk(S, 2 * i, 2 * i >= RAW.value);
      pin(P); pin(S);
    };
    auto bb_fence = [&]() { if (!p.one) mbar_wait(AB, 0); };
    auto merge = [&](auto KK) {
      constexpr int o = KK.value * 8;
      const bool c0 = 16 * KK.value > tz, c1 = 16 * KK.value + 1 > tz;
      mov_if(Y[o], X[o], c0); mov_if(Y[o + 1], X[o + 1], c1);
      if (KK.value > 0) { mov_if(Y[o + 2], X[o + 2], KK.value > w); mov_if(Y[o + 3], X[o + 3], KK.value > w); }
      mov_if(Y[o + 4], X[o + 4], KK.value >= w + 1 - p.one); mov_if(Y[o + 5], X[o + 5], KK.value >= w + 1 - p.one);
      mov_if(Y[o + 6], X[o + 6], c0); mov_if(Y[o + 7], X[o + 7], c1);
    };
    auto pack_edge = [&](auto KK) {
      constexpr int o = KK.value * 8, d = (KK.value & 1) * 4;
      const uint32_t mF = KK.value < w ? 0xffffffffu : 0u, mT = KK.value <= w ? 0xffffffffu : 0u, mA = KK.value == w ? dmask : mF;
      constexpr int t0 = KK.value < 2 ? 0 : 32 - TAILE;
      const uint32_t k0 = pk(Y, o, o >= t0), k1 = pk(Y, o + 2, o + 2 >= t0), k2 = pk(Y, o + 4, o + 4 >= t0), k3 = pk(Y, o + 6, o + 6 >= t0);
      P[d] = k0 & mA; P[d + 1] = k1 & mT; P[d + 2] = k2 & mF; P[d + 3] = k3 & mA;
      P[d + 8] = k0 & ~mA; P[d + 9] = k1 & ~mT; P[d + 10] = k2 & ~mF; P[d + 11] = k3 & ~mA;
    };
    uint32_t F[4] = {0, 0, 0, 0};
    bool fsafe = false;
    auto store_head = [&](int h, bool on) {
      uint32_t* dst = odst + h * 8192;
      st_relaxed_if(dst, nonzero(movm_t(F[0])), on);
      st_relaxed_if(dst + 32, nonzero(movm_t(F[1])), on);
      st_relaxed_if(dst + 512, nonzero(movm_t(F[2])), on);
      st_relaxed_if(dst + 512 + 32, nonzero(movm_t(F[3])), on);
      __syncwarp();
      mbar_arrive_warp_if(BAR(B_PUB + 5) + h * 8, on);
    };
    uint32_t redo = 0;
    auto normalize = [&]() {
      const float la = O[8], lb = O[10];
      const float ia = rcp_fast(la), ib = rcp_fast(lb);
      F[0] = pack_bf16(O[0] * ia, O[1] * ia); F[1] = pack_bf16(O[2] * ib, O[3] * ib);
      F[2] = pack_bf16(O[4] * ia, O[5] * ia); F[3] = pack_bf16(O[6] * ib, O[7] * ib);
      fsafe = fminf(la, lb) >= 0x1p-60f && fmaxf(la, lb) <= 0x1p60f && la == la && lb == lb;
    };
    auto finish_head = [&](int h) {
      const bool safe = __all_sync(0xffffffffu, fsafe);
      store_head(h, safe && h >= 0);
      redo |= (safe ? 0u : 1u) << (h + 1);
    };

    constexpr int KOLD = (KV_K2 - KV_K0) / 16;
    const uint32_t hD = 2048 / 16, hO = r >= 2 ? 8192 / 16 : 0;
    const uint64_t kE = desc64(desc_lo(OFF_KV + KV_K0, 2048) + t * 64, 8, lane), k1 = desc64(desc_lo(OFF_KV + KV_K0, 2048) + (t ? 0 : KOLD + 64), 8, lane);
    const uint64_t k2 = desc64(desc_lo(OFF_KV + KV_K1, 4096), 8, lane), v2 = desc64(desc_lo(OFF_KV + KV_V1, 128), r >= 1 ? 6144 / 16 : 0, lane);
    const uint64_t vD = desc64(desc_lo(OFF_KV + KV_V0, 128) + t * 64, hD, lane), vO = desc64(desc_lo(OFF_KV + KV_V2, 128) + t * 64, hO, lane);
    const uint64_t v1 = desc64(t ? desc_lo(OFF_KV + KV_V0, 128) : desc_lo(OFF_KV + KV_V2, 128) + 64, t ? hD : hO, lane);
    if (aw < 6 && r - (aw >> 1) >= 0) {
      const int nb = aw >> 1, pl = aw & 1;
      const uint32_t tag = ld_relaxed(&g_epoch[cta * 32]) * 2 + 1, bar = BAR(B_KV0 + aw);
#pragma unroll 1
      for (int n = 0; n < SPIN_LIMIT && ld_acquire(&g_flags[((r - nb) * 8 + g) * 32 + 8]) != tag; n++) __nanosleep(100);
      fence_proxy_global();
      const unsigned char* src = g_kv + (uint32_t)(g * 12) * 65536 + pl * 32768 + (uint32_t)(r - nb) * 2048;
      const uint32_t dk = sb + OFF_KV + (nb == 0 ? KV_K0 + pl * 2048 : (nb == 1 ? KV_K1 + pl * 4096 : KV_K2 + pl * 2048));
      const uint32_t dv = sb + OFF_KV + (nb == 0 ? KV_V0 + pl * 2048 : (nb == 1 ? KV_V1 + pl * 6144 : KV_V2 + pl * 8192));
      mbar_wait_sleep(BAR(B_PUB), 0);
      __nanosleep(KDELAY);
#pragma unroll 1
      for (int n = 0; n < SPIN_LIMIT; n++) {
        if (elect_one()) { mbar_expect_tx(bar, 4096); bulk_ld(dk, src, 2048, bar); bulk_ld(dv, src + 65536, 2048, bar); }
        __syncwarp();
        mbar_wait(bar, n & 1);
        uint32_t ok = 1;
#pragma unroll
        for (int k = 0; k < 4; k++) ok = min(ok, lds32u((k < 2 ? dk : dv) + (k & 1) * 1024 + lane * 32 + (lane >> 2) * 4));
        if (__all_sync(0xffffffffu, ok != 0)) { break; }
        fence_proxy_smem();
      }
    }
    nb_sync(NB_Q, 384);
    Qraw = lds128u(sb + OFF_Q0 + aw * XP + lane * 16);
    Q[0] = movm_t(Qraw.x); Q[1] = movm_t(Qraw.y); Q[2] = movm_t(Qraw.z); Q[3] = movm_t(Qraw.w);
    wg_fence();
    mma_qk<0>(Y, Q, kE, p.one); mma_qk<KOLD>(X, Q, kE, p.one);
    wg_commit();
    wg_wait<0>();
    pin(X); pin(Y);

#pragma unroll 1
    for (int h = 0; h < 4; h++) {
      const uint32_t hp = h & 1;
      merge(IC<0>()); merge(IC<1>()); merge(IC<2>()); merge(IC<3>());
      pin(X); pin(Y);
      wg_fence();
      mma_qk<0>(X, Q, k1, p.one);
      wg_commit();
      normalize();
      okA = mbar_test(AB + 16, hp);
      pack_edge(IC<0>()); pack_edge(IC<1>());
      pin(P); pin(O);
      if (!okA) mbar_wait(AB + 16, hp);
      wg_fence();
      mma_pv<0, 0>(O, &P[0], vD); mma_pv<16, 1>(O, &P[4], vD); mma_pv<0, 1>(O, &P[8], vO); mma_pv<16, 1>(O, &P[12], vO);
      wg_commit();
      finish_head(h - 1);
      okB = mbar_test(AB + 8, hp);
      exps(Y, IC<16>(), IC<32 - TAILE>());
      if (!okB) mbar_wait(AB + 8, hp);
      wg_wait<0>(); pin(P); pin(X);
      mbar_arrive_warp(AB + 32);
      pack_edge(IC<2>()); pack_edge(IC<3>());
      pin(P); pin(Y);
      wg_fence();
      mma_qk<64>(Y, Q, k2, p.one);
      mma_pv<32, 1>(O, &P[0], vD); mma_pv<48, 1>(O, &P[4], vD); mma_pv<32, 1>(O, &P[8], vO); mma_pv<48, 1>(O, &P[12], vO);
      wg_commit();
      qp += h < 3 ? 49152 : 0;
      Qraw = make_uint4(__ldcg(qp), __ldcg(qp + 32), __ldcg(qp + 8192), __ldcg(qp + 8224));
      exps(X, IC<0>(), IC<32 - TAIL>());
      bb_fence();
      wg_wait<0>(); pin(P); pin(Y);
      pack(X, IC<32 - TAIL>());
      wg_fence();
      mma_qk<0>(X, Q, k2, p.one);
      mma_pv<0, 1>(O, &P[0], v1); mma_pv<16, 1>(O, &P[4], v1); mma_pv<32, 1>(O, &P[8], v1); mma_pv<48, 1>(O, &P[12], v1);
      wg_commit();
      bb_fence();
      exps(Y, IC<0>(), IC<MID>());
      bb_fence();
      wg_wait<0>(); pin(P); pin(X); pin(Q);
      mbar_arrive_warp(AB + 48);
      mbar_arrive_warp(AB + 40);
      okB = mbar_test(AB + 24, hp);
      pack(Y, IC<MID>());
      if (!okB) mbar_wait(AB + 24, hp);
      wg_fence();
      mma_pv<64, 1>(O, &P[0], v2); mma_pv<80, 1>(O, &P[4], v2); mma_pv<96, 1>(O, &P[8], v2); mma_pv<112, 1>(O, &P[12], v2);
      wg_commit();
      Q[0] = movm_t(Qraw.x); Q[1] = movm_t(Qraw.y); Q[2] = movm_t(Qraw.z); Q[3] = movm_t(Qraw.w);
      pin(Q);
      okA = mbar_test(AB, hp ^ (h < 3));
      exps(X, IC<0>(), IC<32 - TAIL>());
      if (!okA) mbar_wait(AB, hp ^ 1);
      wg_wait<0>(); pin(P); pin(Y);
      wg_fence();
      mma_qk<0>(Y, Q, kE, p.one);
      wg_commit();
      pack(X, IC<32 - TAIL>());
      wg_fence();
      mma_qk<KOLD>(X, Q, kE, p.one);
      mma_pv<0, 1>(O, &P[0], v2); mma_pv<16, 1>(O, &P[4], v2); mma_pv<32, 1>(O, &P[8], v2); mma_pv<48, 1>(O, &P[12], v2);
      wg_commit();
      wg_wait<0>();
      pin(O); pin(P); pin(X); pin(Y);
      mbar_arrive_warp(AB + 56);
    }
    normalize();
    finish_head(3);
#pragma unroll 1
    for (int h = 0; redo >> (h + 1); h++) {
      if ((redo >> (h + 1)) & 1) {
        float G[8];
        attn_exact(g_kv + (uint32_t)(g * 4 + h) * 196608, r * 128 + t * 64 + w * 16 + (lane >> 2), G);
#pragma unroll
        for (int i = 0; i < 4; i++) F[i] = pack_bf16(G[2 * i], G[2 * i + 1]);
        store_head(h, true);
      }
    }
  }
}

typedef CUresult (*EncodeFn)(CUtensorMap*, CUtensorMapDataType, cuuint32_t, void*, const cuuint64_t*, const cuuint64_t*,
                             const cuuint32_t*, const cuuint32_t*, CUtensorMapInterleave, CUtensorMapSwizzle,
                             CUtensorMapL2promotion, CUtensorMapFloatOOBfill);

void encode(EncodeFn fn, CUtensorMap* m, const void* base, int rank, const cuuint64_t* dims, const cuuint64_t* strides, const cuuint32_t* box) {
  cuuint32_t es[5] = {1, 1, 1, 1, 1};
  fn(m, CU_TENSOR_MAP_DATA_TYPE_BFLOAT16, rank, (void*)base, dims, strides, box, es, CU_TENSOR_MAP_INTERLEAVE_NONE,
     box[0] == 32 ? CU_TENSOR_MAP_SWIZZLE_64B : CU_TENSOR_MAP_SWIZZLE_128B, CU_TENSOR_MAP_L2_PROMOTION_L2_128B, CU_TENSOR_MAP_FLOAT_OOB_FILL_NONE);
}

}

extern "C" void kernel_launch(void* const* d_in, const int* in_sizes, int n_in, void* d_out, int out_size) {
  (void)in_sizes; (void)n_in; (void)out_size;
  Params p;
  p.x = (const __nv_bfloat16*)d_in[0];
  p.wqkv = (const __nv_bfloat16*)d_in[1];
  p.wo = (const __nv_bfloat16*)d_in[2];
  p.w1 = (const __nv_bfloat16*)d_in[4];
  p.b1 = (const __nv_bfloat16*)d_in[5];
  p.w2 = (const __nv_bfloat16*)d_in[6];
  p.b2 = (const __nv_bfloat16*)d_in[7];
  p.one = 1;

  EncodeFn fn = nullptr;
  cudaDriverEntryPointQueryResult qr;
  cudaGetDriverEntryPoint("cuTensorMapEncodeTiled", (void**)&fn, cudaEnableDefault, &qr);
  CUtensorMap mx, mqkv, mw1, mw2, mw2s, mwo, mout;
  { cuuint64_t d[2] = {512, 2048}, s[1] = {1024}; cuuint32_t b[2] = {64, 128}; encode(fn, &mx, p.x, 2, d, s, b); b[1] = 64; encode(fn, &mout, d_out, 2, d, s, b); }
  { cuuint64_t d[2] = {1536, 512}, s[1] = {3072}; cuuint32_t b[2] = {32, 64}; encode(fn, &mqkv, p.wqkv, 2, d, s, b); }
  { cuuint64_t d[2] = {1376, 512}, s[1] = {2752}; cuuint32_t b[2] = {32, 64}; encode(fn, &mw1, p.w1, 2, d, s, b); }
  { cuuint64_t d[2] = {512, 1376}, s[1] = {1024}; cuuint32_t b[2] = {64, 64}; encode(fn, &mw2, p.w2, 2, d, s, b); b[1] = 48; encode(fn, &mw2s, p.w2, 2, d, s, b); }
  { cuuint64_t d[3] = {512, 64, 8}, s[2] = {1024, 65536}; cuuint32_t b[3] = {64, 16, 4}; encode(fn, &mwo, p.wo, 3, d, s, b); }

  cudaFuncSetAttribute(fused_kernel, cudaFuncAttributeMaxDynamicSharedMemorySize, SMEM_BYTES);
  cudaLaunchConfig_t cfg = {};
  cfg.gridDim = dim3(128);
  cfg.blockDim = dim3(NTHREADS);
  cfg.dynamicSmemBytes = SMEM_BYTES;
  cfg.stream = cudaStreamPerThread;
  cudaLaunchAttribute at[1];
  at[0].id = cudaLaunchAttributeClusterDimension;
  at[0].val.clusterDim.x = 2; at[0].val.clusterDim.y = 1; at[0].val.clusterDim.z = 1;
  cfg.attrs = at; cfg.numAttrs = 1;
  cudaLaunchKernelEx(&cfg, fused_kernel, mx, mqkv, mw1, mw2, mw2s, mwo, mout, p);
}
```
